```python
import torch

def _softmax(x, axis=-1):
    return torch.softmax(x, dim=axis)
def _gelu(x):
    return torch.nn.functional.gelu(x, approximate="tanh")
def _silu(x):
    return torch.nn.functional.silu(x)
def _sigmoid(x):
    return torch.sigmoid(x)
def _layernorm(x, axis=-1, eps=1e-5):
    m = x.mean(dim=axis, keepdim=True)
    v = x.var(dim=axis, keepdim=True, unbiased=False)
    return (x - m) / torch.sqrt(v + eps)
def _scatter_add(tgt, idx, src, axis=0):
    return tgt.clone().index_add_(axis, idx, src)
def _segment_sum(src, seg, n):
    out = torch.zeros((n,) + src.shape[1:], dtype=src.dtype)
    return out.index_add_(0, seg, src)
def _pad(x, pw):
    flat = tuple(v for pair in reversed(pw) for v in pair)
    return torch.nn.functional.pad(x, flat)

kernel_name = 'gated_mix__sliding_block_cached__glu_gated_bilinear__decode'

def setup_inputs():

    _w = (lambda a: (lambda t: t.to(torch.bfloat16) if t.is_floating_point() else t)(torch.as_tensor(a)))
    def _A_setup():
        B, Sq, D = 2, 1, 512
        Hq, Hkv, Sk, Dh = 32, 32, 4096, 128
        assert Hq % Hkv == 0, (Hq, Hkv)
        return {
            "x": _w((lambda *s: torch.randn(*s, dtype=torch.bfloat16) * 0.05)(B, Sq, D)),
            "k_cache": _w((lambda *s: torch.randn(*s, dtype=torch.bfloat16) * 6.4)(B, Hkv, Sk, Dh)),
            "v_cache": _w((lambda *s: torch.randn(*s, dtype=torch.bfloat16) * 0.05)(B, Hkv, Sk, Dh)),
            "wq": _w((lambda *s: torch.randn(*s, dtype=torch.bfloat16) * 6.4)(D, Hq * Dh) * (D ** -0.5)),
            "wo": _w((lambda *s: torch.randn(*s, dtype=torch.bfloat16) * 0.05)(Hq * Dh, D) * ((Hq * Dh) ** -0.5)),
        }
    _A_in = _A_setup()

    def _B_setup():
        B, S, D, F = 2, 1, 512, 1376
        return {
            "x": _w((lambda *s: torch.randn(*s, dtype=torch.bfloat16) * 0.05)(B, S, D)),
            "w_gate": _w((lambda *s: torch.randn(*s, dtype=torch.bfloat16) * 0.4)(D, F) * (D ** -0.5)),
            "w_up": _w((lambda *s: torch.randn(*s, dtype=torch.bfloat16) * 0.4)(D, F) * (D ** -0.5)),
            "w_down": _w((lambda *s: torch.randn(*s, dtype=torch.bfloat16) * 0.4)(F, D) * (F ** -0.5)),
        }
    _B_in = _B_setup()

    return {
        "A_x": _A_in["x"],
        "A_k_cache": _A_in["k_cache"],
        "A_v_cache": _A_in["v_cache"],
        "A_wq": _A_in["wq"],
        "A_wo": _A_in["wo"],
        "B_x": _B_in["x"],
        "B_w_gate": _B_in["w_gate"],
        "B_w_up": _B_in["w_up"],
        "B_w_down": _B_in["w_down"],
        "gate_w": _w((lambda *s: torch.randn(*s, dtype=torch.bfloat16) * 0.05)(512) * 16.0),
    }

def reference(A_x, A_k_cache, A_v_cache, A_wq, A_wo, B_x, B_w_gate, B_w_up, B_w_down, gate_w):
    def _A_ref(x, k_cache, v_cache, wq, wo):
        B, Sq, D = x.shape
        Hq, Dh = 32, 128
        Hkv, Sk = k_cache.shape[1], k_cache.shape[2]
        W = min(4096, max(256, Sk // 4))
        rep = Hq // Hkv
        q = (lambda x, *d: x.permute(*d))((x @ wq).reshape(B, Sq, Hq, Dh), 0, 2, 1, 3)
        k = (lambda x, n, axis: torch.repeat_interleave(x, n, dim=axis))(k_cache[:, :, Sk - W:, :], rep, axis=1)
        v = (lambda x, n, axis: torch.repeat_interleave(x, n, dim=axis))(v_cache[:, :, Sk - W:, :], rep, axis=1)
        scores = torch.einsum("bhqd,bhkd->bhqk", q, k) * (Dh ** -0.5)
        p = _softmax(scores, axis=-1)
        o = torch.einsum("bhqk,bhkd->bhqd", p, v)
        return (lambda x, *d: x.permute(*d))(o, 0, 2, 1, 3).reshape(B, Sq, Hq * Dh) @ wo

    def _B_ref(x, w_gate, w_up, w_down):
        g = torch.einsum("bsd,df->bsf", x, w_gate)
        u = torch.einsum("bsd,df->bsf", x, w_up)
        h = g * u
        return torch.einsum("bsf,fd->bsd", h, w_down)

    x = A_x
    g = _sigmoid((x * gate_w).sum(-1, keepdims=True))
    a = _A_ref(x, A_k_cache, A_v_cache, A_wq, A_wo)
    b = _B_ref(x, B_w_gate, B_w_up, B_w_down)
    return g * a + (1 - g) * b
```

```cpp
#include <cuda_runtime.h>
#include <cuda_bf16.h>
#include <stdint.h>

namespace {

constexpr int D_MODEL = 512;
constexpr int N_HEAD = 32;
constexpr int SK = 4096;
constexpr int DH = 128;
constexpr int WIN = 1024;
constexpr int FF = 1376;
constexpr int NCTA = 128;
constexpr int NTHREADS = 288;

constexpr int SLOT = 32768 + 128;
constexpr int NSLOT = 5;
constexpr int VSUB = 4096 + 16;
constexpr int KSUB = 16384 + 64;
constexpr int OFF_RING = 0;
constexpr int OFF_WA = NSLOT * SLOT;
constexpr int OFF_WB = OFF_WA + 32768;
constexpr int GU_PITCH = 208;
constexpr int OFF_QS = OFF_WB + 128 * GU_PITCH;
constexpr int OFF_PS = OFF_QS + 256;
constexpr int OFF_OS = OFF_PS + 1024;
constexpr int OFF_HS = OFF_OS + 2 * 272;
constexpr int OFF_MISC = OFF_HS + 2 * 112;
constexpr int OFF_BAR = OFF_MISC + 128;
constexpr int SMEM_BYTES = OFF_BAR + 16 * 8;
static_assert(OFF_WA % 128 == 0 && OFF_QS % 16 == 0 && OFF_OS % 16 == 0 && OFF_BAR % 8 == 0, "align");
static_assert(SMEM_BYTES <= 232448, "smem");

enum { BAR_K = 0, BAR_V = 4, BAR_EMPTY = 8, BAR_F = 11, BAR_ALL = 12 };

__device__ uint32_t g_epoch[NCTA * 8];
__device__ __align__(128) uint32_t g_e1[NCTA * 512];
__device__ __align__(128) uint32_t g_e2[NCTA * 8];
__device__ __align__(128) uint32_t g_e3[NCTA * 128];
__device__ __align__(128) uint32_t g_e4[NCTA * 256];
#define TLC(i)
#define TLP(i)

constexpr int SPIN_LIMIT = 1 << 22;

__device__ __forceinline__ void mbar_init(uint32_t a, int c) {
    asm volatile("mbarrier.init.shared::cta.b64 [%0], %1;" ::"r"(a), "r"(c) : "memory");
}
__device__ __forceinline__ void mbar_expect(uint32_t a, uint32_t bytes) {
    asm volatile("mbarrier.arrive.expect_tx.shared::cta.b64 _, [%0], %1;" ::"r"(a), "r"(bytes) : "memory");
}
__device__ __forceinline__ void mbar_arrive(uint32_t a) {
    asm volatile("mbarrier.arrive.shared::cta.b64 _, [%0];" ::"r"(a) : "memory");
}
__device__ __forceinline__ void mbar_wait(uint32_t a, uint32_t parity) {
    uint32_t ok;
    int it = 0;
    do {
        asm volatile("{.reg .pred p; mbarrier.try_wait.parity.shared::cta.b64 p, [%1], %2; selp.u32 %0,1,0,p;}"
                     : "=r"(ok) : "r"(a), "r"(parity) : "memory");
        if (++it > SPIN_LIMIT) __trap();
    } while (!ok);
}
__device__ __forceinline__ void bulk_load(uint32_t dst, const void* src, uint32_t bytes, uint32_t bar) {
    asm volatile("cp.async.bulk.shared::cluster.global.mbarrier::complete_tx::bytes [%0], [%1], %2, [%3];"
                 ::"r"(dst), "l"(src), "r"(bytes), "r"(bar) : "memory");
}
__device__ __forceinline__ void cp16(uint32_t dst, const void* src) {
    asm volatile("cp.async.cg.shared.global [%0], [%1], 16;" ::"r"(dst), "l"(src) : "memory");
}
__device__ __forceinline__ void cp16_z(uint32_t dst, const void* src, uint32_t sz) {
    asm volatile("cp.async.cg.shared.global.L2::128B [%0], [%1], 16, %2;" ::"r"(dst), "l"(src), "r"(sz) : "memory");
}
__device__ __forceinline__ void cp_wait_all() { asm volatile("cp.async.wait_all;" ::: "memory"); }
__device__ __forceinline__ void bar_sync(int id, int n) { asm volatile("bar.sync %0, %1;" ::"r"(id), "r"(n) : "memory"); }
__device__ __forceinline__ void bar_arrive(int id, int n) { asm volatile("bar.arrive %0, %1;" ::"r"(id), "r"(n) : "memory"); }
__device__ __forceinline__ void ldsm_t(uint32_t (&r)[4], uint32_t addr) {
    asm volatile("ldmatrix.sync.aligned.m8n8.x4.trans.shared.b16 {%0,%1,%2,%3}, [%4];"
                 : "=r"(r[0]), "=r"(r[1]), "=r"(r[2]), "=r"(r[3]) : "r"(addr) : "memory");
}
__device__ __forceinline__ uint4 lds128(uint32_t addr) {
    uint4 v;
    asm volatile("ld.shared.v4.u32 {%0,%1,%2,%3}, [%4];" : "=r"(v.x), "=r"(v.y), "=r"(v.z), "=r"(v.w) : "r"(addr) : "memory");
    return v;
}
__device__ __forceinline__ uint32_t lds32(uint32_t addr) {
    uint32_t v;
    asm volatile("ld.shared.u32 %0, [%1];" : "=r"(v) : "r"(addr) : "memory");
    return v;
}
__device__ __forceinline__ float ldsf(uint32_t addr) { return __uint_as_float(lds32(addr)); }
__device__ __forceinline__ void stsf(uint32_t addr, float v) {
    asm volatile("st.shared.f32 [%0], %1;" ::"r"(addr), "f"(v) : "memory");
}
__device__ __forceinline__ void sts_bf16(uint32_t addr, float v) {
    unsigned short u = __bfloat16_as_ushort(__float2bfloat16_rn(v));
    asm volatile("st.shared.u16 [%0], %1;" ::"r"(addr), "h"(u) : "memory");
}
__device__ __forceinline__ void mma16816(float (&c)[4], uint32_t a0, uint32_t a1, uint32_t a2, uint32_t a3,
                                         uint32_t b0, uint32_t b1) {
    asm volatile("mma.sync.aligned.m16n8k16.row.col.f32.bf16.bf16.f32 {%0,%1,%2,%3}, {%4,%5,%6,%7}, {%8,%9}, {%0,%1,%2,%3};"
                 : "+f"(c[0]), "+f"(c[1]), "+f"(c[2]), "+f"(c[3])
                 : "r"(a0), "r"(a1), "r"(a2), "r"(a3), "r"(b0), "r"(b1));
}
__device__ __forceinline__ float bf16r(float v) { return __bfloat162float(__float2bfloat16_rn(v)); }
__device__ __forceinline__ float bf_lo(uint32_t u) { return __uint_as_float(u << 16); }
__device__ __forceinline__ float bf_hi(uint32_t u) { return __uint_as_float(u & 0xffff0000u); }
__device__ __forceinline__ float pick4(const float (&c)[4], int t) {
    float lo = (t & 1) ? c[1] : c[0], hi = (t & 1) ? c[3] : c[2];
    return (t & 2) ? hi : lo;
}
__device__ __forceinline__ void xput(uint32_t* p, float v, uint32_t tag) {
    uint32_t u = (__float_as_uint(v) & ~3u) | tag;
    asm volatile("st.relaxed.gpu.global.u32 [%0], %1;" ::"l"(p), "r"(u) : "memory");
}
__device__ __forceinline__ uint32_t xld(const uint32_t* p) {
    uint32_t u;
    asm volatile("ld.relaxed.gpu.global.u32 %0, [%1];" : "=r"(u) : "l"(p) : "memory");
    return u;
}
__device__ __forceinline__ float xval(uint32_t u) { return __uint_as_float(u & ~3u); }
template <int N>
__device__ __forceinline__ float xsum(const uint32_t* p, int stride, uint32_t tag) {
    uint32_t u[N];
    int it = 0;
    while (true) {
        uint32_t bad = 0;
#pragma unroll
        for (int i = 0; i < N; i++) u[i] = xld(p + i * stride);
#pragma unroll
        for (int i = 0; i < N; i++) bad |= (u[i] ^ tag);
        if ((bad & 3u) == 0) break;
        if (++it > SPIN_LIMIT) __trap();
    }
    float s = xval(u[0]);
#pragma unroll
    for (int i = 1; i < N; i++) s += xval(u[i]);
    return s;
}

#define WO_TRIGGER 2

__global__ void __launch_bounds__(NTHREADS, 1)
fused_decode_kernel(const __nv_bfloat16* __restrict__ x, const __nv_bfloat16* __restrict__ kc,
                    const __nv_bfloat16* __restrict__ vc, const __nv_bfloat16* __restrict__ wq,
                    const __nv_bfloat16* __restrict__ wo, const __nv_bfloat16* __restrict__ wg,
                    const __nv_bfloat16* __restrict__ wu, const __nv_bfloat16* __restrict__ wd,
                    const __nv_bfloat16* __restrict__ gw, __nv_bfloat16* __restrict__ out) {
    extern __shared__ __align__(128) unsigned char smem[];
    const uint32_t sb = (uint32_t)__cvta_generic_to_shared(smem);
    const int tid = threadIdx.x, lane = tid & 31, w = tid >> 5;
    const int cta = blockIdx.x, h = cta >> 2, j = cta & 3;
    const uint32_t bars = sb + OFF_BAR;
    const int u0 = h < 12 ? 6 * h : 12 + 5 * h;
    const int nu = h < 12 ? 6 : 5;

    if (w == 8) {
        TLP(0);
        const size_t kvoff = ((size_t)((j >> 1) * N_HEAD + h) * SK + (SK - WIN) + (j & 1) * 512) * DH;
        const unsigned char* kp = reinterpret_cast<const unsigned char*>(kc + kvoff);
        const unsigned char* vp = reinterpret_cast<const unsigned char*>(vc + kvoff);
        if (lane == 0) {
#pragma unroll
            for (int i = 0; i < 8; i++) mbar_init(bars + 8 * i, 1);
#pragma unroll
            for (int i = 0; i < 3; i++) mbar_init(bars + 8 * (BAR_EMPTY + i), 8);
            mbar_init(bars + 8 * BAR_F, 1);
            asm volatile("fence.mbarrier_init.release.cluster;" ::: "memory");
#pragma unroll
            for (int c = 0; c < 4; c++) {
                mbar_expect(bars + 8 * (BAR_K + c), 32768);
                bulk_load(sb + c * SLOT, kp + c * 32768, 16384, bars + 8 * (BAR_K + c));
                bulk_load(sb + c * SLOT + KSUB, kp + c * 32768 + 16384, 16384, bars + 8 * (BAR_K + c));
            }
            mbar_expect(bars + 8 * BAR_V, 32768);
#pragma unroll 1
            for (int i = 0; i < 8; i++) bulk_load(sb + 4 * SLOT + i * VSUB, vp + i * 4096, 4096, bars + 8 * BAR_V);
        }
        __syncwarp();
        TLP(1);
        const uint32_t tag = (xld(&g_epoch[cta * 8]) + 1) & 3u;
        {
            const uint4* gp = reinterpret_cast<const uint4*>(gw) + lane * 2;
            const uint4* xp = reinterpret_cast<const uint4*>(x) + lane * 2;
            uint4 g0 = __ldg(gp), g1 = __ldg(gp + 1);
            float acc[2];
#pragma unroll
            for (int b = 0; b < 2; b++) {
                uint4 a0 = __ldg(xp + b * 64), a1 = __ldg(xp + b * 64 + 1);
                const uint32_t av[8] = {a0.x, a0.y, a0.z, a0.w, a1.x, a1.y, a1.z, a1.w};
                const uint32_t gv[8] = {g0.x, g0.y, g0.z, g0.w, g1.x, g1.y, g1.z, g1.w};
                float s = 0.f;
#pragma unroll
                for (int i = 0; i < 8; i++) {
                    s += bf16r(bf_lo(av[i]) * bf_lo(gv[i]));
                    s += bf16r(bf_hi(av[i]) * bf_hi(gv[i]));
                }
                acc[b] = s;
            }
#pragma unroll
            for (int o = 16; o; o >>= 1) {
                acc[0] += __shfl_xor_sync(0xffffffffu, acc[0], o);
                acc[1] += __shfl_xor_sync(0xffffffffu, acc[1], o);
            }
            if (lane < 2) {
                float z = bf16r(lane ? acc[1] : acc[0]);
                float g = bf16r(1.f / (1.f + __expf(-z)));
                stsf(sb + OFF_MISC + 64 + lane * 4, g);
                stsf(sb + OFF_MISC + 72 + lane * 4, bf16r(1.f - g));
            }
        }
        __syncwarp();
        bar_arrive(1, NTHREADS);
        if (lane == 0) {
#pragma unroll 1
            for (int c = 1; c < 4; c++) {
                mbar_wait(bars + 8 * (BAR_EMPTY + c - 1), 0);
                mbar_expect(bars + 8 * (BAR_V + c), 32768);
#pragma unroll 1
                for (int i = 0; i < 8; i++)
                    bulk_load(sb + (c - 1) * SLOT + i * VSUB, vp + c * 32768 + i * 4096, 4096, bars + 8 * (BAR_V + c));
            }
        }
        __syncwarp();
        TLP(2);
        bar_sync(4, NTHREADS);
        if (lane == 0) {
            float m = ldsf(sb + OFF_MISC), l = ldsf(sb + OFF_MISC + 32);
#pragma unroll
            for (int i = 1; i < 8; i++) {
                m = fmaxf(m, ldsf(sb + OFF_MISC + 4 * i));
                l += ldsf(sb + OFF_MISC + 32 + 4 * i);
            }
            xput(&g_e2[cta * 8], m, tag);
            xput(&g_e2[cta * 8 + 1], l, tag);
            float m2 = xsum<1>(&g_e2[(cta ^ 1) * 8], 0, tag);
            float l2 = xsum<1>(&g_e2[(cta ^ 1) * 8 + 1], 0, tag);
            float mm = fmaxf(m, m2);
            float e1 = __expf(m - mm), e2 = __expf(m2 - mm);
            stsf(sb + OFF_MISC + 80, e1 / (l * e1 + l2 * e2));
            mbar_arrive(bars + 8 * BAR_F);
        }
        __syncwarp();
        TLP(3);
        {
            float s = xsum<8>(&g_e4[cta * 256 + lane], 32, tag);
            s += __shfl_xor_sync(0xffffffffu, s, 8);
            s += __shfl_xor_sync(0xffffffffu, s, 16);
            if (lane < 8) out[(lane >> 2) * D_MODEL + j * 128 + h * 4 + (lane & 3)] = __float2bfloat16_rn(s);
        }
        TLP(4);
        return;
    }

    TLC(8);
    const int g = lane >> 2, t = lane & 3;
    {
        const int c = tid & 15, r0 = tid >> 4;
        const __nv_bfloat16* src = wq + (size_t)(j * 128 + r0) * (N_HEAD * DH) + h * DH + c * 8;
        const uint32_t dst = sb + OFF_WA + r0 * 256 + ((c ^ (r0 & 7)) << 4);
#pragma unroll
        for (int i = 0; i < 8; i++) cp16(dst + i * 4096, src + (size_t)i * 16 * (N_HEAD * DH));
#pragma unroll
        for (int i = 0; i < 6; i++) {
            const int idx = tid + 256 * i, row = idx / 12, cc = idx - row * 12;
            const int mat = cc >= 6, unit = cc - 6 * mat;
            const bool ok = unit < nu;
            const __nv_bfloat16* s2 = (mat ? wu : wg) + (size_t)(j * 128 + row) * FF + (u0 + (ok ? unit : 0)) * 8;
            cp16_z(sb + OFF_WB + row * GU_PITCH + cc * 16, s2, ok ? 16u : 0u);
        }
    }
    uint32_t xb[16];
    {
        const uint32_t* xp = reinterpret_cast<const uint32_t*>(x + (g & 1) * D_MODEL + j * 128) + t;
#pragma unroll
        for (int i = 0; i < 16; i++) xb[i] = __ldg(xp + i * 4);
    }
    const uint32_t epoch = xld(&g_epoch[cta * 8]);
    const uint32_t tag = (epoch + 1) & 3u;
    const int mi = lane >> 3, li = lane & 7;
    const uint32_t wa_addr = sb + OFF_WA + ((mi >> 1) * 8 + li) * 256 + (((2 * w + (mi & 1)) ^ li) << 4);
    cp_wait_all();
    bar_sync(1, NTHREADS);
    TLC(9);
    if (tid == 0) g_epoch[cta * 8] = epoch + 1;
    {
        float c0[4] = {0.f, 0.f, 0.f, 0.f}, c1[4] = {0.f, 0.f, 0.f, 0.f};
#pragma unroll
        for (int s = 0; s < 8; s++) {
            uint32_t a[4];
            ldsm_t(a, wa_addr + s * 4096);
            mma16816(c0, a[0], a[1], a[2], a[3], xb[2 * s], xb[2 * s + 1]);
        }
        xput(&g_e1[cta * 512 + (t & 1) * 128 + w * 16 + g + 8 * (t >> 1)], pick4(c0, t), tag);
        if (w < 6) {
            const uint32_t ga = sb + OFF_WB + ((mi >> 1) * 8 + li) * GU_PITCH + w * 32 + (mi & 1) * 16;
#pragma unroll
            for (int s = 0; s < 8; s++) {
                uint32_t a[4];
                ldsm_t(a, ga + s * 16 * GU_PITCH);
                mma16816(c1, a[0], a[1], a[2], a[3], xb[2 * s], xb[2 * s + 1]);
            }
            xput(&g_e1[cta * 512 + 256 + (t & 1) * 96 + w * 16 + g + 8 * (t >> 1)], pick4(c1, t), tag);
        }
    }
    if (tid < 128) {
        float q = xsum<4>(&g_e1[(cta & ~3) * 512 + (j >> 1) * 128 + tid], 512, tag);
        sts_bf16(sb + OFF_QS + tid * 2, q);
    } else if (tid < 224) {
        const int i = tid - 128, b = i >= 48, f = i - 48 * b;
        float gg = xsum<4>(&g_e1[(cta & ~3) * 512 + 256 + b * 96 + f], 512, tag);
        float uu = xsum<4>(&g_e1[(cta & ~3) * 512 + 256 + b * 96 + 48 + f], 512, tag);
        sts_bf16(sb + OFF_HS + b * 112 + f * 2, bf16r(gg) * bf16r(uu));
    }
    bar_sync(2, 256);
    TLC(10);

    float s0 = 0.f, s1 = 0.f;
    {
        uint4 qf[4];
#pragma unroll
        for (int i = 0; i < 4; i++) qf[i] = lds128(sb + OFF_QS + (4 * i + t) * 16);
        const uint32_t ka = sb + (g & 1) * KSUB + (8 * w + (g >> 1)) * 256 + t * 16;
#pragma unroll 1
        for (int c = 0; c < 4; c++) {
            mbar_wait(bars + 8 * (BAR_K + c), 0);
            float c0[4] = {0.f, 0.f, 0.f, 0.f}, c1[4] = {0.f, 0.f, 0.f, 0.f};
            uint4 lo[4], hi[4];
#pragma unroll
            for (int i = 0; i < 4; i++) {
                lo[i] = lds128(ka + c * SLOT + i * 64);
                hi[i] = lds128(ka + c * SLOT + i * 64 + 1024);
            }
#pragma unroll
            for (int i = 0; i < 4; i++) {
                mma16816(c0, lo[i].x, hi[i].x, lo[i].y, hi[i].y, qf[i].x, qf[i].y);
                mma16816(c1, lo[i].z, hi[i].z, lo[i].w, hi[i].w, qf[i].z, qf[i].w);
            }
            if (c < 3) {
                __syncwarp();
                if (lane == 0) mbar_arrive(bars + 8 * (BAR_EMPTY + c));
            }
            if (t == c) {
                s0 = c0[0] + c1[0];
                s1 = c0[2] + c1[2];
            }
        }
    }
    TLC(11);
    {
        const float scale = 0.08838834764831845f;
        s0 = bf16r(bf16r(s0) * scale);
        s1 = bf16r(bf16r(s1) * scale);
        float m = fmaxf(s0, s1);
#pragma unroll
        for (int o = 16; o; o >>= 1) m = fmaxf(m, __shfl_xor_sync(0xffffffffu, m, o));
        if (lane == 0) stsf(sb + OFF_MISC + 4 * w, m);
        bar_sync(3, 256);
        uint4 m0 = lds128(sb + OFF_MISC), m1 = lds128(sb + OFF_MISC + 16);
        m = fmaxf(fmaxf(fmaxf(__uint_as_float(m0.x), __uint_as_float(m0.y)), fmaxf(__uint_as_float(m0.z), __uint_as_float(m0.w))),
                  fmaxf(fmaxf(__uint_as_float(m1.x), __uint_as_float(m1.y)), fmaxf(__uint_as_float(m1.z), __uint_as_float(m1.w))));
        const float p0 = __expf(s0 - m), p1 = __expf(s1 - m);
        const int key = 64 * (g & 1) + 8 * w + (g >> 1);
        const int i = key >> 4, r = key & 15;
        const int pos = t * 128 + (r >> 2) * 32 + (i >> 1) * 8 + ((r >> 1) & 1) * 4 + (r & 1) * 2 + (i & 1);
        sts_bf16(sb + OFF_PS + pos * 2, p0);
        sts_bf16(sb + OFF_PS + (pos + 32) * 2, p1);
        float l = p0 + p1;
#pragma unroll
        for (int o = 16; o; o >>= 1) l += __shfl_xor_sync(0xffffffffu, l, o);
        if (lane == 0) stsf(sb + OFF_MISC + 32 + 4 * w, l);
        bar_sync(4, NTHREADS);
    }
    TLC(12);

    {
        float c0[4] = {0.f, 0.f, 0.f, 0.f}, c1[4] = {0.f, 0.f, 0.f, 0.f};
        const uint32_t va = sb + li * VSUB + (mi >> 1) * 256 + (2 * w + (mi & 1)) * 16;
#pragma unroll 1
        for (int c = 0; c < 4; c++) {
            uint4 pf[4];
#pragma unroll
            for (int i = 0; i < 4; i++) pf[i] = lds128(sb + OFF_PS + c * 256 + i * 64 + t * 16);
            mbar_wait(bars + 8 * (BAR_V + c), 0);
            if (c == WO_TRIGGER) {
                const int cc = tid & 15, r0 = tid >> 4;
                const uint32_t sw = r0 * 256 + ((cc ^ (r0 & 7)) << 4);
#pragma unroll
                for (int i = 0; i < 3; i++) {
                    const bool ok = r0 + 16 * i < nu * 8;
                    const __nv_bfloat16* s2 = wd + (size_t)(u0 * 8 + (ok ? r0 + 16 * i : 0)) * D_MODEL + j * 128 + cc * 8;
                    cp16_z(sb + OFF_WB + sw + i * 4096, s2, ok ? 16u : 0u);
                }
                const __nv_bfloat16* src = wo + (size_t)(h * DH + r0) * D_MODEL + j * 128 + cc * 8;
#pragma unroll
                for (int i = 0; i < 8; i++) cp16(sb + OFF_WA + sw + i * 4096, src + i * 16 * D_MODEL);
            }
            const uint32_t base = va + (c == 0 ? 4 : c - 1) * SLOT;
#pragma unroll
            for (int i = 0; i < 4; i++) {
                uint32_t a[4], b[4];
                ldsm_t(a, base + i * 1024);
                ldsm_t(b, base + i * 1024 + 512);
                mma16816(c0, a[0], a[1], a[2], a[3], pf[i].x, pf[i].y);
                mma16816(c1, b[0], b[1], b[2], b[3], pf[i].z, pf[i].w);
            }
        }
        TLC(13);
        mbar_wait(bars + 8 * BAR_F, 0);
        const float f = ldsf(sb + OFF_MISC + 80);
        if (t < 2) xput(&g_e3[cta * 128 + w * 16 + g + 8 * t], f * (t ? c0[2] + c1[2] : c0[0] + c1[0]), tag);
    }
    {
        float o = xsum<2>(&g_e3[((cta & ~3) + (tid >> 7) * 2) * 128 + (tid & 127)], 128, tag);
        sts_bf16(sb + OFF_OS + (tid >> 7) * 272 + (tid & 127) * 2, o);
    }
    TLC(14);
    cp_wait_all();
    bar_sync(5, 256);
    TLC(15);

    {
        float c0[4] = {0.f, 0.f, 0.f, 0.f}, c1[4] = {0.f, 0.f, 0.f, 0.f}, c2[4] = {0.f, 0.f, 0.f, 0.f};
        const uint32_t oa = sb + OFF_OS + (g & 1) * 272 + t * 4;
        const uint32_t ha = sb + OFF_HS + (g & 1) * 112 + t * 4;
#pragma unroll
        for (int s = 0; s < 4; s++) {
            uint32_t a[4], b[4];
            ldsm_t(a, wa_addr + s * 8192);
            ldsm_t(b, wa_addr + s * 8192 + 4096);
            mma16816(c0, a[0], a[1], a[2], a[3], lds32(oa + s * 64), lds32(oa + s * 64 + 16));
            mma16816(c1, b[0], b[1], b[2], b[3], lds32(oa + s * 64 + 32), lds32(oa + s * 64 + 48));
            if (s < 3) {
                uint32_t d[4];
                ldsm_t(d, wa_addr + (OFF_WB - OFF_WA) + s * 4096);
                mma16816(c2, d[0], d[1], d[2], d[3], lds32(ha + s * 32), lds32(ha + s * 32 + 16));
            }
        }
        const float ga = ldsf(sb + OFF_MISC + 64 + (t & 1) * 4), gb = ldsf(sb + OFF_MISC + 72 + (t & 1) * 4);
        const float v = ga * (pick4(c0, t) + pick4(c1, t)) + gb * pick4(c2, t);
        const int col = g + 8 * (t >> 1);
        const int dst = (4 * w + (col >> 2)) * 4 + j;
        xput(&g_e4[dst * 256 + h * 8 + (t & 1) * 4 + (col & 3)], v, tag);
    }
    TLC(16);
}

}

extern "C" void kernel_launch(void* const* d_in, const int* in_sizes, int n_in, void* d_out, int out_size) {
    (void)in_sizes; (void)n_in; (void)out_size;
    static bool configured = false;
    if (!configured) {
        cudaFuncSetAttribute(fused_decode_kernel, cudaFuncAttributeMaxDynamicSharedMemorySize, SMEM_BYTES);
        configured = true;
    }
    const __nv_bfloat16* x = (const __nv_bfloat16*)d_in[0];
    const __nv_bfloat16* kc = (const __nv_bfloat16*)d_in[1];
    const __nv_bfloat16* vc = (const __nv_bfloat16*)d_in[2];
    const __nv_bfloat16* wq = (const __nv_bfloat16*)d_in[3];
    const __nv_bfloat16* wo = (const __nv_bfloat16*)d_in[4];
    const __nv_bfloat16* wg = (const __nv_bfloat16*)d_in[6];
    const __nv_bfloat16* wu = (const __nv_bfloat16*)d_in[7];
    const __nv_bfloat16* wd = (const __nv_bfloat16*)d_in[8];
    const __nv_bfloat16* gw = (const __nv_bfloat16*)d_in[9];
    fused_decode_kernel<<<NCTA, NTHREADS, SMEM_BYTES>>>(x, kc, vc, wq, wo, wg, wu, wd, gw, (__nv_bfloat16*)d_out);
}
```

```cpp
#include <cuda.h>
#include <cuda_runtime.h>
#include <cuda_bf16.h>
#include <stdint.h>
#include <stdio.h>

namespace {

constexpr int D_MODEL = 512;
constexpr int N_HEAD = 32;
constexpr int SK = 4096;
constexpr int DH = 128;
constexpr int WIN = 1024;
constexpr int FF = 1376;
constexpr int NCTA = 128;
constexpr int NTHREADS = 320;

constexpr int SLOT = 32768 + 128;
constexpr int NSLOT = 5;
constexpr int VSUB = 4096 + 16;
constexpr int KSUB = 16384 + 64;
constexpr int OFF_WA = 0;
constexpr int OFF_RING = 32768;
constexpr int OFF_WB = OFF_RING + NSLOT * SLOT + 128;
constexpr int OFF_QX = OFF_WB + 12288;
constexpr int OFF_QS = OFF_QX + 512;
constexpr int OFF_PS = OFF_QS + 256;
constexpr int OFF_OS = OFF_PS + 1024;
constexpr int OFF_HS = OFF_OS + 2 * 320;
constexpr int HS_PITCH = 720;
constexpr int OFF_MISC = OFF_HS + 2 * HS_PITCH;
constexpr int OFF_ST = OFF_MISC + 128;
constexpr int OFF_BAR = OFF_ST + 128;
constexpr int SMEM_BYTES = OFF_BAR + 72 * 8;
static_assert(OFF_WB % 256 == 0 && OFF_QS % 16 == 0 && OFF_OS % 16 == 0 && OFF_BAR % 8 == 0, "align");
static_assert(SMEM_BYTES <= 232448, "smem");

enum {
    BAR_EMPTY = 16,
    BAR_F = 19,
    BAR_G = 20,
    BAR_D = 21,
    BAR_Q = 24,
    BAR_WFREE = 25,
    BAR_W = 26,
    BAR_Z = 30,
    BAR_O = 31,
    BAR_QFREE = 32,
    NBAR = 33
};

struct Scratch {
    uint32_t epoch[NCTA * 8];
    uint32_t hx[2 * FF];
    uint32_t zero[32];
    unsigned long long acc[256 * 16];
    float side[2 * D_MODEL];
};
__device__ __align__(128) Scratch g_scratch;

constexpr int SPIN_LIMIT = 1 << 22;

__device__ __forceinline__ void mbar_init(uint32_t a, int c) {
    asm volatile("mbarrier.init.shared::cta.b64 [%0], %1;" ::"r"(a), "r"(c) : "memory");
}
__device__ __forceinline__ void mbar_expect(uint32_t a, uint32_t bytes) {
    asm volatile("mbarrier.arrive.expect_tx.shared::cta.b64 _, [%0], %1;" ::"r"(a), "r"(bytes) : "memory");
}
__device__ __forceinline__ void mbar_arrive(uint32_t a) {
    asm volatile("mbarrier.arrive.shared::cta.b64 _, [%0];" ::"r"(a) : "memory");
}
__device__ __forceinline__ void mbar_wait(uint32_t a, uint32_t parity) {
    uint32_t ok;
    int it = 0;
    do {
        asm volatile("{.reg .pred p; mbarrier.try_wait.parity.shared::cta.b64 p, [%1], %2; selp.u32 %0,1,0,p;}"
                     : "=r"(ok) : "r"(a), "r"(parity) : "memory");
        if (++it > SPIN_LIMIT) __trap();
    } while (!ok);
}
__device__ __forceinline__ void mbar_wait_cluster(uint32_t a, uint32_t parity) {
    uint32_t ok;
    int it = 0;
    do {
        asm volatile("{.reg .pred p; mbarrier.try_wait.parity.acquire.cluster.shared::cta.b64 p, [%1], %2; selp.u32 %0,1,0,p;}"
                     : "=r"(ok) : "r"(a), "r"(parity) : "memory");
        if (++it > SPIN_LIMIT) __trap();
    } while (!ok);
}
__device__ __forceinline__ uint64_t stream_policy() {
    uint64_t p;
    asm("createpolicy.fractional.L2::evict_first.b64 %0, 1.0;" : "=l"(p));
    return p;
}
__device__ __forceinline__ void bulk_load(uint32_t dst, const void* src, uint32_t bytes, uint32_t bar) {
    asm volatile("cp.async.bulk.shared::cluster.global.mbarrier::complete_tx::bytes.L2::cache_hint [%0], [%1], %2, [%3], %4;"
                 ::"r"(dst), "l"(src), "r"(bytes), "r"(bar), "l"(stream_policy()) : "memory");
}
__device__ __forceinline__ void cp16(uint32_t dst, const void* src) {
    asm volatile("cp.async.cg.shared.global [%0], [%1], 16;" ::"r"(dst), "l"(src) : "memory");
}
__device__ __forceinline__ void tma2(uint32_t dst, const CUtensorMap* m, int c0, int c1, uint32_t bar) {
    asm volatile("cp.async.bulk.tensor.2d.shared::cluster.global.mbarrier::complete_tx::bytes [%0], [%1, {%3, %4}], [%2];"
                 ::"r"(dst), "l"(m), "r"(bar), "r"(c0), "r"(c1) : "memory");
}
__device__ __forceinline__ void tma3(uint32_t dst, const CUtensorMap* m, int c0, int c1, int c2, uint32_t bar) {
    asm volatile("cp.async.bulk.tensor.3d.shared::cluster.global.mbarrier::complete_tx::bytes [%0], [%1, {%3, %4, %5}], [%2];"
                 ::"r"(dst), "l"(m), "r"(bar), "r"(c0), "r"(c1), "r"(c2) : "memory");
}
__device__ __forceinline__ void map_prefetch(const CUtensorMap* m) { asm volatile("prefetch.tensormap [%0];" ::"l"(m) : "memory"); }
__device__ __forceinline__ void cluster_arrive() { asm volatile("barrier.cluster.arrive.relaxed.aligned;" ::: "memory"); }
__device__ __forceinline__ void cluster_wait() { asm volatile("barrier.cluster.wait.aligned;" ::: "memory"); }
__device__ __forceinline__ void red_out(__nv_bfloat16* p2, int odd, float v) {
    const uint32_t u = __bfloat16_as_ushort(__float2bfloat16_rn(v));
    asm volatile("red.relaxed.gpu.global.add.noftz.bf16x2 [%0], %1;" ::"l"(p2), "r"(odd ? (u << 16) | 0x8000u : u | 0x80000000u) : "memory");
}
__device__ __forceinline__ void cp_wait_all() { asm volatile("cp.async.wait_all;" ::: "memory"); }
__device__ __forceinline__ void bar_sync(int id, int n) { asm volatile("bar.sync %0, %1;" ::"r"(id), "r"(n) : "memory"); }
__device__ __forceinline__ void bar_arrive(int id, int n) { asm volatile("bar.arrive %0, %1;" ::"r"(id), "r"(n) : "memory"); }
__device__ __forceinline__ void ldsm_t(uint32_t (&r)[4], uint32_t addr) {
    asm volatile("ldmatrix.sync.aligned.m8n8.x4.trans.shared.b16 {%0,%1,%2,%3}, [%4];"
                 : "=r"(r[0]), "=r"(r[1]), "=r"(r[2]), "=r"(r[3]) : "r"(addr) : "memory");
}
__device__ __forceinline__ uint4 lds128(uint32_t addr) {
    uint4 v;
    asm volatile("ld.shared.v4.u32 {%0,%1,%2,%3}, [%4];" : "=r"(v.x), "=r"(v.y), "=r"(v.z), "=r"(v.w) : "r"(addr) : "memory");
    return v;
}
__device__ __forceinline__ uint32_t lds32(uint32_t addr) {
    uint32_t v;
    asm volatile("ld.shared.u32 %0, [%1];" : "=r"(v) : "r"(addr) : "memory");
    return v;
}
__device__ __forceinline__ float ldsf(uint32_t addr) { return __uint_as_float(lds32(addr)); }
__device__ __forceinline__ void stsf(uint32_t addr, float v) {
    asm volatile("st.shared.f32 [%0], %1;" ::"r"(addr), "f"(v) : "memory");
}
__device__ __forceinline__ void sts_bf16(uint32_t addr, float v) {
    unsigned short u = __bfloat16_as_ushort(__float2bfloat16_rn(v));
    asm volatile("st.shared.u16 [%0], %1;" ::"r"(addr), "h"(u) : "memory");
}
__device__ __forceinline__ void mma16816(float (&c)[4], uint32_t a0, uint32_t a1, uint32_t a2, uint32_t a3,
                                         uint32_t b0, uint32_t b1) {
    asm volatile("mma.sync.aligned.m16n8k16.row.col.f32.bf16.bf16.f32 {%0,%1,%2,%3}, {%4,%5,%6,%7}, {%8,%9}, {%0,%1,%2,%3};"
                 : "+f"(c[0]), "+f"(c[1]), "+f"(c[2]), "+f"(c[3])
                 : "r"(a0), "r"(a1), "r"(a2), "r"(a3), "r"(b0), "r"(b1));
}
__device__ __forceinline__ float bf16r(float v) { return __bfloat162float(__float2bfloat16_rn(v)); }
__device__ __forceinline__ float bf_lo(uint32_t u) { return __uint_as_float(u << 16); }
__device__ __forceinline__ float bf_hi(uint32_t u) { return __uint_as_float(u & 0xffff0000u); }
__device__ __forceinline__ float pick4(const float (&c)[4], int t) {
    float lo = (t & 1) ? c[1] : c[0], hi = (t & 1) ? c[3] : c[2];
    return (t & 2) ? hi : lo;
}
__device__ __forceinline__ uint32_t now_ns() {
    uint32_t t;
    asm volatile("mov.u32 %0, %%globaltimer_lo;" : "=r"(t));
    return t;
}
__device__ __forceinline__ void pace(uint32_t t0, int dt) {
    int it = 0;
    while ((int)(now_ns() - t0) < dt && ++it < 4096) {}
}
__device__ __forceinline__ void xput(uint32_t* p, float v, uint32_t tag) {
    uint32_t u = (__float_as_uint(v) & ~3u) | tag;
    asm volatile("st.relaxed.gpu.global.u32 [%0], %1;" ::"l"(p), "r"(u) : "memory");
}
__device__ __forceinline__ uint32_t xld(const uint32_t* p) {
    uint32_t u;
    asm volatile("ld.relaxed.gpu.global.u32 %0, [%1];" : "=r"(u) : "l"(p) : "memory");
    return u;
}
__device__ __forceinline__ uint4 xld4(const uint32_t* p) {
    uint4 u;
    asm volatile("ld.relaxed.gpu.global.v4.u32 {%0,%1,%2,%3}, [%4];" : "=r"(u.x), "=r"(u.y), "=r"(u.z), "=r"(u.w) : "l"(p) : "memory");
    return u;
}

constexpr int TAU = 690;
constexpr int B0 = 1400;
constexpr int GPOS = 6;
constexpr int GT = TAU * 11 / 8;
constexpr int WO_T = 12190;
constexpr int WO_STEP = 310;
constexpr int WD_T = WO_T + 3 * WO_STEP + 480;
constexpr int HPOLL = 12;

struct Perm { uint8_t v[NCTA / 2]; };
struct Slice { uint8_t v[NCTA]; };

__global__ void __cluster_dims__(2, 1, 1) __launch_bounds__(NTHREADS, 1)
fused_decode_kernel(const __nv_bfloat16* __restrict__ wq, const __grid_constant__ Perm perm, const __nv_bfloat16* __restrict__ kc,
                    const __nv_bfloat16* __restrict__ x, Scratch* __restrict__ sc,
                    const __nv_bfloat16* __restrict__ gw, const __nv_bfloat16* __restrict__ vc,
                    __nv_bfloat16* __restrict__ out, const __grid_constant__ Slice slice,
                    const __grid_constant__ CUtensorMap mg, const __grid_constant__ CUtensorMap mu,
                    const __grid_constant__ CUtensorMap mo, const __grid_constant__ CUtensorMap md) {
    extern __shared__ __align__(1024) unsigned char smem[];
    const uint32_t sb = (uint32_t)__cvta_generic_to_shared(smem);
    const int tid = threadIdx.x, lane = tid & 31, w = tid >> 5;
    const int cta = 2 * perm.v[blockIdx.x >> 1] + (blockIdx.x & 1), h = cta >> 2, j = cta & 3;
    if (tid < 256) {
        const uint32_t c = tid & 15, r0 = tid >> 4;
        const uint32_t off = (blockIdx.x & 1) * (256 * N_HEAD * DH * 2) + r0 * (N_HEAD * DH * 2) + c * 16 + h * (DH * 2);
        const unsigned char* src = reinterpret_cast<const unsigned char*>(wq) + off;
        const uint32_t dst = sb + OFF_WA + (c >> 3) * 4096 + r0 * 128 + (((c ^ r0) & 7) << 4);
#pragma unroll 1
        for (int i = 0; i < 8; i++) {
            cp16(dst + i * 8192, src);
            cp16(dst + i * 8192 + 2048, src + 16 * (N_HEAD * DH * 2));
            src += 32 * (N_HEAD * DH * 2);
        }
    }
    const uint32_t bars = sb + OFF_BAR, ring = sb + OFF_RING;
    const int fs = slice.v[blockIdx.x];
    const bool has_ffn = fs < FF / 16;
    const int dc = 4 * (h & 7) + j, dr = h >> 3;

    if (w == 8) {
        const uint32_t t0 = now_ns();
        const size_t kvoff = ((size_t)((j >> 1) * N_HEAD + h) * SK + (SK - WIN) + (j & 1) * 512) * DH;
        const unsigned char* kp = reinterpret_cast<const unsigned char*>(kc + kvoff);
        const unsigned char* vp = reinterpret_cast<const unsigned char*>(vc + kvoff);
        if (lane == 0) {
            mbar_init(bars, 1);
            mbar_expect(bars, 16384);
            bulk_load(ring + 2 * SLOT, kp, 16384, bars);
#pragma unroll
            for (int i = 1; i < NBAR; i++)
                mbar_init(bars + 8 * i, i == BAR_Z ? 32 : i == BAR_WFREE ? 2 : (i >= BAR_EMPTY && i < BAR_F) || i == BAR_QFREE ? 8 : 1);
            mbar_expect(bars + 8 * BAR_Q, 512);
            mbar_expect(bars + 8 * BAR_F, 128);
            mbar_expect(bars + 8 * BAR_O, 512);
            asm volatile("fence.mbarrier_init.release.cluster;" ::: "memory");
        }
        __syncwarp();
        bar_arrive(1, NTHREADS);
        cluster_arrive();
        if (lane == 0) {
            map_prefetch(&mg);
            map_prefetch(&mu);
#pragma unroll 1
            for (int n = 1; n < 8; n++) {
                if (n == GPOS) {
                    mbar_wait(bars + 8 * BAR_QFREE, 0);
                    if (has_ffn) {
                        asm volatile("fence.proxy.async.shared::cta;" ::: "memory");
                        mbar_expect(bars + 8 * BAR_G, 32768);
#pragma unroll 1
                        for (int q = 0; q < 4; q++) {
                            pace(t0, TAU * (n + 2) + q * (GT / 4) - B0);
                            tma2(sb + OFF_WA + q * 8192, (q & 1) ? &mu : &mg, fs * 16, (q >> 1) * 256, bars + 8 * BAR_G);
                        }
                    }
                    map_prefetch(&mo);
                    map_prefetch(&md);
                }
                pace(t0, TAU * (n + 2) + (n >= GPOS ? GT : 0) - B0);
                mbar_expect(bars + 8 * n, 16384);
                bulk_load(ring + (n < 6 ? (n >> 1) + 2 : 0) * SLOT + (n & 1) * KSUB, kp + n * 16384, 16384, bars + 8 * n);
            }
#pragma unroll 1
            for (int n = 0; n < 8; n++) {
                const int c = n >> 1;
                pace(t0, TAU * (n + 10) + GT - B0);
                if (c) mbar_wait(bars + 8 * (BAR_EMPTY + c - 1), 0);
                const uint32_t dst = ring + (c + 1) * SLOT + (n & 1) * (4 * VSUB);
                mbar_expect(bars + 8 * (8 + n), 16384);
#pragma unroll
                for (int i = 0; i < 4; i++) bulk_load(dst + i * VSUB, vp + n * 16384 + i * 4096, 4096, bars + 8 * (8 + n));
            }
            mbar_wait(bars + 8 * BAR_WFREE, 0);
            asm volatile("fence.proxy.async.shared::cta;" ::: "memory");
#pragma unroll 1
            for (int q = 0; q < 4; q++) {
                pace(t0, WO_T + WO_STEP * q);
                mbar_expect(bars + 8 * (BAR_W + q), 16384);
                tma3(sb + OFF_WA + q * 16384, &mo, 0, h * DH + 32 * q, 4 * (j & 1), bars + 8 * (BAR_W + q));
            }
#pragma unroll 1
            for (int q = 0; q < 3; q++) {
                pace(t0, WD_T);
                mbar_expect(bars + 8 * (BAR_D + q), 4096);
                tma3(sb + OFF_WB + q * 4096, &md, dc * 16, 128 * q, dr, bars + 8 * (BAR_D + q));
            }
        }
        return;
    }
    if (w == 9) {
        cluster_arrive();
        const uint32_t epoch = xld(&sc->epoch[cta * 8]) + 1, tag = epoch & 3u;
        bar_sync(1, NTHREADS);
        if (fs == FF / 16) {
#pragma unroll
            for (int k = 0; k < 4; k++)
                asm volatile("st.relaxed.gpu.global.v2.u64 [%0], {%1, %1};" ::"l"(out + (lane + 32 * k) * 8), "l"(0ull) : "memory");
#pragma unroll
            for (int k = 0; k < 16; k++)
                asm volatile("st.relaxed.gpu.global.v2.u64 [%0], {%1, %1};" ::"l"(&sc->acc[((lane >> 1) + 16 * k) * 16 + (lane & 1) * 2]), "l"(0ull) : "memory");
            asm volatile("fence.acq_rel.gpu;" ::: "memory");
            __syncwarp();
            if (lane < 8) xput(&sc->zero[lane], 0.f, tag);
        }
        {
            const uint4* gp = reinterpret_cast<const uint4*>(gw) + lane * 2;
            const uint4* xp = reinterpret_cast<const uint4*>(x) + lane * 2;
            uint4 g0 = __ldg(gp), g1 = __ldg(gp + 1);
            float acc[2];
#pragma unroll
            for (int b = 0; b < 2; b++) {
                uint4 a0 = __ldg(xp + b * 64), a1 = __ldg(xp + b * 64 + 1);
                const uint32_t av[8] = {a0.x, a0.y, a0.z, a0.w, a1.x, a1.y, a1.z, a1.w};
                const uint32_t gv[8] = {g0.x, g0.y, g0.z, g0.w, g1.x, g1.y, g1.z, g1.w};
                float s = 0.f;
#pragma unroll
                for (int i = 0; i < 8; i++) {
                    s += bf16r(bf_lo(av[i]) * bf_lo(gv[i]));
                    s += bf16r(bf_hi(av[i]) * bf_hi(gv[i]));
                }
                acc[b] = s;
            }
#pragma unroll
            for (int o = 16; o; o >>= 1) {
                acc[0] += __shfl_xor_sync(0xffffffffu, acc[0], o);
                acc[1] += __shfl_xor_sync(0xffffffffu, acc[1], o);
            }
            if (lane < 2) {
                float z = bf16r(lane ? acc[1] : acc[0]);
                float g = bf16r(1.f / (1.f + __expf(-z)));
                stsf(sb + OFF_MISC + 64 + lane * 4, g);
                stsf(sb + OFF_MISC + 72 + lane * 4, bf16r(1.f - g));
            }
        }

        {
            if (lane == 0) sc->epoch[cta * 8] = epoch;
            if (has_ffn) {
                const int g = lane >> 2, t = lane & 3, mi = lane >> 3, li = lane & 7;
                const uint32_t* xp = reinterpret_cast<const uint32_t*>(x + (g & 1) * D_MODEL) + t;
                const uint32_t ga = sb + OFF_WA + ((mi >> 1) * 8 + li) * 32 + (((mi ^ (li >> 2)) & 1) << 4);
                uint32_t xb[64];
#pragma unroll
                for (int i = 0; i < 64; i++) xb[i] = __ldg(xp + i * 4);
                float c0[4] = {0.f, 0.f, 0.f, 0.f}, c1[4] = {0.f, 0.f, 0.f, 0.f};
                mbar_wait(bars + 8 * BAR_G, 0);
#pragma unroll
                for (int s = 0; s < 32; s++) {
                    uint32_t a[4], b[4];
                    ldsm_t(a, ga + (s >> 4) * 16384 + (s & 15) * 512);
                    ldsm_t(b, ga + (s >> 4) * 16384 + (s & 15) * 512 + 8192);
                    mma16816(c0, a[0], a[1], a[2], a[3], xb[2 * s], xb[2 * s + 1]);
                    mma16816(c1, b[0], b[1], b[2], b[3], xb[2 * s], xb[2 * s + 1]);
                }
                xput(&sc->hx[(t & 1) * FF + fs * 16 + g + 8 * (t >> 1)], bf16r(bf16r(pick4(c0, t)) * bf16r(pick4(c1, t))), tag);
            }
            __syncwarp();
            if (lane == 0) mbar_arrive(bars + 8 * BAR_WFREE);
        }
#pragma unroll 1
        for (int pass = 0; pass < 2; pass++) {
            int live;
            asm volatile("mov.u32 %0, %1;" : "=r"(live) : "r"(pass));
            if (live) {
                if (lane < 8) stsf(sb + OFF_HS + (lane >> 2) * HS_PITCH + 688 + (lane & 3) * 4, 0.f);
                uint4 u[6];
                mbar_wait(bars + 8 * HPOLL, 0);
                int it = 0;
                while (true) {
#pragma unroll
                    for (int k = 0; k < 6; k++) {
                        const int c = min(lane + 32 * (k >> 1), 85);
                        u[k] = xld4(&sc->hx[(k & 1) * FF + dr * 344 + c * 4]);
                    }
                    uint32_t bad;
                    asm volatile("ld.acquire.gpu.global.u32 %0, [%1];" : "=r"(bad) : "l"(&sc->zero[0]) : "memory");
                    bad ^= tag;
#pragma unroll
                    for (int k = 0; k < 6; k++) bad |= (u[k].x ^ tag) | (u[k].y ^ tag) | (u[k].z ^ tag) | (u[k].w ^ tag);
                    if (__all_sync(0xffffffffu, (bad & 3u) == 0)) break;
                    if (++it > SPIN_LIMIT) __trap();
                }
#pragma unroll
                for (int k = 0; k < 6; k++) {
                    const int c = min(lane + 32 * (k >> 1), 85);
                    asm volatile("st.shared.v2.u32 [%0], {%1, %2};" ::"r"(sb + OFF_HS + (k & 1) * HS_PITCH + c * 8),
                                 "r"(__byte_perm(u[k].x, u[k].y, 0x7632)), "r"(__byte_perm(u[k].z, u[k].w, 0x7632)) : "memory");
                }
                mbar_arrive(bars + 8 * BAR_Z);
            }
            __syncwarp();
            {
                const int g = lane >> 2, t = lane & 3, mi = lane >> 3, li = lane & 7;
                const uint32_t da = sb + OFF_WB + ((mi >> 1) * 8 + li) * 32 + (((mi ^ (li >> 2)) & 1) << 4);
                const uint32_t ha = sb + OFF_HS + (g & 1) * HS_PITCH + t * 4;
                __nv_bfloat16* op = out + (t & 1) * D_MODEL + dc * 16 + (g & 6) + 8 * (t >> 1);
                uint32_t hb[44];
#pragma unroll
                for (int i = 0; i < 44; i++) hb[i] = lds32(ha + i * 16);
                const float gb = ldsf(sb + OFF_MISC + 72 + (t & 1) * 4);
                constexpr int NC = 4;
                float c[NC][4];
#pragma unroll
                for (int i = 0; i < NC; i++) c[i][0] = c[i][1] = c[i][2] = c[i][3] = 0.f;
#pragma unroll
                for (int p = 0; p < 3; p++) {
                    if (live) mbar_wait(bars + 8 * (BAR_D + p), 0);
                    uint32_t a[8][4];
#pragma unroll
                    for (int i = 0; i < (p < 2 ? 8 : 6); i++) ldsm_t(a[i], da + (p * 8 + i) * 512);
#pragma unroll
                    for (int i = 0; i < (p < 2 ? 8 : 6); i++)
                        mma16816(c[i % NC], a[i][0], a[i][1], a[i][2], a[i][3], hb[16 * p + 2 * i], hb[16 * p + 2 * i + 1]);
                }
                float r[NC];
#pragma unroll
                for (int i = 0; i < NC; i++) r[i] = pick4(c[i], t);
#pragma unroll
                for (int o = NC / 2; o; o >>= 1)
#pragma unroll
                    for (int i = 0; i < o; i++) r[i] += r[i + o];
                if (live) red_out(op, g & 1, gb * r[0]);
            }
        }
        return;
    }

    const int g = lane >> 2, t = lane & 3;
    const int mi = lane >> 3, li = lane & 7;
    {
        uint32_t xb[32];
        const uint32_t* xp = reinterpret_cast<const uint32_t*>(x + j * 256) + t;
#pragma unroll
        for (int i = 0; i < 32; i++)
            asm volatile("ld.global.nc.u32 %0, [%1];" : "=r"(xb[i]) : "l"(xp + i * 4) : "memory");
        const uint32_t wa_addr = sb + OFF_WA + (w >> 2) * 4096 + ((mi >> 1) * 8 + li) * 128 + (((2 * (w & 3) + (mi & 1)) ^ li) << 4);
        const uint32_t qx = sb + OFF_QX + (w * 16 + g + 8 * (t & 1)) * 4;
        uint32_t dst, bar;
        asm("mapa.shared::cluster.u32 %0, %1, %2;" : "=r"(dst) : "r"(qx), "r"(~j & 1));
        asm("mapa.shared::cluster.u32 %0, %1, %2;" : "=r"(bar) : "r"(bars + 8 * BAR_Q), "r"(~j & 1));
        cluster_arrive();
        cp_wait_all();
        bar_sync(1, NTHREADS);
        float c0[4] = {0.f, 0.f, 0.f, 0.f}, c1[4] = {0.f, 0.f, 0.f, 0.f};
#pragma unroll
        for (int s = 0; s < 8; s++) {
            uint32_t a[4], b[4];
            ldsm_t(a, wa_addr + s * 8192);
            ldsm_t(b, wa_addr + s * 8192 + 2048);
            mma16816(c0, a[0], a[1], a[2], a[3], xb[4 * s], xb[4 * s + 1]);
            mma16816(c1, b[0], b[1], b[2], b[3], xb[4 * s + 2], xb[4 * s + 3]);
        }
        const float q = (t & 1) ? c0[2] + c1[2] : c0[0] + c1[0];
        cluster_wait();
        if (t < 2)
            asm volatile("st.async.weak.shared::cluster.mbarrier::complete_tx::bytes.b32 [%0], %1, [%2];"
                         ::"r"(dst), "r"(__float_as_uint(q)), "r"(bar) : "memory");
        if (lane == 0) mbar_arrive(bars + 8 * BAR_QFREE);
        mbar_wait_cluster(bars + 8 * BAR_Q, 0);
        if (t < 2) sts_bf16(sb + OFF_QS + (w * 16 + g + 8 * t) * 2, q + ldsf(qx));
    }
    bar_sync(2, 256);

    float s0 = 0.f, s1 = 0.f;
    {
        uint4 qf[4];
#pragma unroll
        for (int i = 0; i < 4; i++) qf[i] = lds128(sb + OFF_QS + (4 * i + t) * 16);
        const uint32_t ka = ring + (g & 1) * KSUB + (8 * w + (g >> 1)) * 256 + t * 16;
#pragma unroll 1
        for (int c = 0; c < 4; c++) {
            mbar_wait(bars + 16 * c, 0);
            mbar_wait(bars + 16 * c + 8, 0);
            float c0[4] = {0.f, 0.f, 0.f, 0.f}, c1[4] = {0.f, 0.f, 0.f, 0.f};
            uint4 lo[4], hi[4];
            const uint32_t kb = ka + (c < 3 ? c + 2 : 0) * SLOT;
#pragma unroll
            for (int i = 0; i < 4; i++) {
                lo[i] = lds128(kb + i * 64);
                hi[i] = lds128(kb + i * 64 + 1024);
            }
#pragma unroll
            for (int i = 0; i < 4; i++) {
                mma16816(c0, lo[i].x, hi[i].x, lo[i].y, hi[i].y, qf[i].x, qf[i].y);
                mma16816(c1, lo[i].z, hi[i].z, lo[i].w, hi[i].w, qf[i].z, qf[i].w);
            }
            if (c < 3) {
                __syncwarp();
                if (lane == 0) mbar_arrive(bars + 8 * (BAR_EMPTY + c));
            }
            if (t == c) {
                s0 = c0[0] + c1[0];
                s1 = c0[2] + c1[2];
            }
        }
    }
    {
        const float scale = 0.08838834764831845f;
        s0 = bf16r(bf16r(s0) * scale);
        s1 = bf16r(bf16r(s1) * scale);
        float m = fmaxf(s0, s1);
#pragma unroll
        for (int o = 16; o; o >>= 1) m = fmaxf(m, __shfl_xor_sync(0xffffffffu, m, o));
        if (lane == 0) stsf(sb + OFF_MISC + 4 * w, m);
        bar_sync(3, 256);
        uint4 m0 = lds128(sb + OFF_MISC), m1 = lds128(sb + OFF_MISC + 16);
        m = fmaxf(fmaxf(fmaxf(__uint_as_float(m0.x), __uint_as_float(m0.y)), fmaxf(__uint_as_float(m0.z), __uint_as_float(m0.w))),
                  fmaxf(fmaxf(__uint_as_float(m1.x), __uint_as_float(m1.y)), fmaxf(__uint_as_float(m1.z), __uint_as_float(m1.w))));
        const float p0 = __expf(s0 - m), p1 = __expf(s1 - m);
        const int key = 64 * (g & 1) + 8 * w + (g >> 1);
        const int i = key >> 4, r = key & 15;
        const int pos = t * 128 + (r >> 2) * 32 + (i >> 1) * 8 + ((r >> 1) & 1) * 4 + (r & 1) * 2 + (i & 1);
        sts_bf16(sb + OFF_PS + pos * 2, p0);
        sts_bf16(sb + OFF_PS + (pos + 32) * 2, p1);
        float l = p0 + p1;
#pragma unroll
        for (int o = 16; o; o >>= 1) l += __shfl_xor_sync(0xffffffffu, l, o);
        if (lane < 2) {
            uint32_t dst, bar;
            asm("mapa.shared::cluster.u32 %0, %1, %2;" : "=r"(dst) : "r"(sb + OFF_ST + (j & 1) * 64 + w * 8), "r"(lane));
            asm("mapa.shared::cluster.u32 %0, %1, %2;" : "=r"(bar) : "r"(bars + 8 * BAR_F), "r"(lane));
            asm volatile("st.async.weak.shared::cluster.mbarrier::complete_tx::bytes.v2.b32 [%0], {%1, %2}, [%3];"
                         ::"r"(dst), "r"(__float_as_uint(m)), "r"(__float_as_uint(l)), "r"(bar) : "memory");
        }
        bar_sync(4, 256);
    }
    if (tid == 0) mbar_arrive(bars + 8 * BAR_WFREE);

    {
        float c0[4] = {0.f, 0.f, 0.f, 0.f}, c1[4] = {0.f, 0.f, 0.f, 0.f};
        const uint32_t va = ring + li * VSUB + (mi >> 1) * 256 + (2 * w + (mi & 1)) * 16;
        uint32_t o_dst, o_bar;
        asm("mapa.shared::cluster.u32 %0, %1, %2;" : "=r"(o_dst) : "r"(sb + OFF_OS + (j & 1) * 320 + (g >> 1) * 80 + (2 * w + (t & 1)) * 4), "r"(t >> 1));
        asm("mapa.shared::cluster.u32 %0, %1, %2;" : "=r"(o_bar) : "r"(bars + 8 * BAR_O), "r"(t >> 1));
        float f = 0.f;
#pragma unroll 1
        for (int n = 0; n < 8; n++) {
            if (n == 6) {
                mbar_wait_cluster(bars + 8 * BAR_F, 0);
                const float mo = ldsf(sb + OFF_ST + (j & 1) * 64), mp = ldsf(sb + OFF_ST + (~j & 1) * 64);
                const float mm = fmaxf(mo, mp);
                float l = ldsf(sb + OFF_ST + (lane & 15) * 8 + 4) * __expf(ldsf(sb + OFF_ST + (lane & 15) * 8) - mm);
#pragma unroll
                for (int o = 8; o; o >>= 1) l += __shfl_xor_sync(0xffffffffu, l, o);
                f = __expf(mo - mm) / l;
            }
            mbar_wait(bars + 8 * (8 + n), 0);
            if (n & 1) {
                const int c = n >> 1;
                uint4 pf[4];
#pragma unroll
                for (int i = 0; i < 4; i++) pf[i] = lds128(sb + OFF_PS + c * 256 + i * 64 + t * 16);
                const uint32_t base = va + (c + 1) * SLOT;
#pragma unroll
                for (int i = 0; i < 4; i++) {
                    uint32_t a[4], b[4];
                    ldsm_t(a, base + i * 1024);
                    ldsm_t(b, base + i * 1024 + 512);
                    mma16816(c0, a[0], a[1], a[2], a[3], pf[i].x, pf[i].y);
                    mma16816(c1, b[0], b[1], b[2], b[3], pf[i].z, pf[i].w);
                }
            }
        }
        const float v = f * ((t & 1) ? c0[2] + c1[2] : c0[0] + c1[0]);
        const __nv_bfloat162 pr = __floats2bfloat162_rn(v, __shfl_xor_sync(0xffffffffu, v, 4));
        if (!(g & 1))
            asm volatile("st.async.weak.shared::cluster.mbarrier::complete_tx::bytes.b32 [%0], %1, [%2];"
                         ::"r"(o_dst), "r"(*reinterpret_cast<const uint32_t*>(&pr)), "r"(o_bar) : "memory");
    }
    {
        float c0[4] = {0.f, 0.f, 0.f, 0.f}, c1[4] = {0.f, 0.f, 0.f, 0.f};
        const int e = (j * 8 + w) * 32 + lane;
        unsigned long long* acc = &sc->acc[(e >> 2) * 16 + (e & 3)];
        const int oi = j * 256 + w * 32 + t * 8 + g;
        const uint32_t wo_addr = sb + OFF_WA + (w >> 1) * 4096 + ((mi >> 1) * 8 + li) * 128 + (((4 * (w & 1) + (mi & 1)) ^ li) << 4);
        uint32_t a[4][4];
        float c2[4] = {0.f, 0.f, 0.f, 0.f}, c3[4] = {0.f, 0.f, 0.f, 0.f};
        mbar_wait(bars + 8 * BAR_Z, 0);
        const float ga = ldsf(sb + OFF_MISC + 64 + (j >> 1) * 4);
        mbar_wait(bars + 8 * BAR_W, 0);
        ldsm_t(a[0], wo_addr);
        ldsm_t(a[1], wo_addr ^ 32);
        ldsm_t(a[2], wo_addr + 2048);
        ldsm_t(a[3], (wo_addr ^ 32) + 2048);
        mbar_wait_cluster(bars + 8 * BAR_O, 0);
        uint4 ob[4];
#pragma unroll
        for (int i = 0; i < 4; i++) ob[i] = lds128(sb + OFF_OS + (g & 1) * 320 + t * 80 + i * 16);
#pragma unroll
        for (int s = 0; s < 4; s++) {
            if (s) {
                mbar_wait(bars + 8 * (BAR_W + s), 0);
                ldsm_t(a[0], wo_addr + s * 16384);
                ldsm_t(a[1], (wo_addr ^ 32) + s * 16384);
                ldsm_t(a[2], wo_addr + s * 16384 + 2048);
                ldsm_t(a[3], (wo_addr ^ 32) + s * 16384 + 2048);
            }
            mma16816(c0, a[0][0], a[0][1], a[0][2], a[0][3], ob[s].x, ob[s].y);
            mma16816(c1, a[1][0], a[1][1], a[1][2], a[1][3], ob[s].x, ob[s].y);
            mma16816(c2, a[2][0], a[2][1], a[2][2], a[2][3], ob[s].z, ob[s].w);
            mma16816(c3, a[3][0], a[3][1], a[3][2], a[3][3], ob[s].z, ob[s].w);
        }
#pragma unroll
        for (int i = 0; i < 4; i++) { c0[i] += c2[i]; c1[i] += c3[i]; }
        const float lo = (t & 1) ? c0[2] + c0[3] : c0[0] + c0[1], hi = (t & 1) ? c1[2] + c1[3] : c1[0] + c1[1];
        const float v = ga * ((t & 2) ? hi : lo);
        const float av = fabsf(v);
        unsigned long long add = ((unsigned long long)__float2ll_rn(v * 68719476736.f) << 12) | 1ull;
        const uint32_t top = __reduce_max_sync(0xffffffffu, __float_as_uint(av));
        if (top - 0x34800000u >= 0x10000000u && top != 0) {
            add = 65ull;
            atomicAdd(&sc->side[oi], v);
            __threadfence();
        }
        unsigned long long old;
        asm volatile("atom.relaxed.gpu.global.add.u64 %0, [%1], %2;" : "=l"(old) : "l"(acc), "l"(add) : "memory");
        old += add;
        if ((old & 63u) == N_HEAD) {
            float r = (float)((long long)old >> 12) * 1.4551915228366852e-11f;
            if (old & 0xfc0u) {
                __threadfence();
                r += atomicExch(&sc->side[oi], 0.f);
            }
            red_out(out + (oi & ~1), oi & 1, r);
        }
    }
}

typedef CUresult (*EncodeFn)(CUtensorMap*, CUtensorMapDataType, cuuint32_t, void*, const cuuint64_t*, const cuuint64_t*,
                             const cuuint32_t*, const cuuint32_t*, CUtensorMapInterleave, CUtensorMapSwizzle,
                             CUtensorMapL2promotion, CUtensorMapFloatOOBfill);
void encode(EncodeFn fn, CUtensorMap* m, void* p, int rank, cuuint64_t d0, cuuint64_t d1, cuuint64_t d2, cuuint64_t s1,
            cuuint64_t s2, cuuint32_t b0, cuuint32_t b1, cuuint32_t b2, CUtensorMapSwizzle sw, CUtensorMapL2promotion promo) {
    const cuuint64_t dim[3] = {d0, d1, d2}, str[2] = {s1, s2};
    const cuuint32_t box[3] = {b0, b1, b2}, es[3] = {1, 1, 1};
    CUresult r = fn(m, CU_TENSOR_MAP_DATA_TYPE_BFLOAT16, rank, p, dim, str, box, es, CU_TENSOR_MAP_INTERLEAVE_NONE, sw,
                    promo, CU_TENSOR_MAP_FLOAT_OOB_FILL_NONE);
    if (r != CUDA_SUCCESS) fprintf(stderr, "tensor map encode failed: %d\n", (int)r);
}

}

extern "C" void kernel_launch(void* const* d_in, const int* in_sizes, int n_in, void* d_out, int out_size) {
    (void)in_sizes; (void)n_in; (void)out_size;
    static Scratch* scratch = nullptr;
    static EncodeFn enc = nullptr;
    if (!scratch) {
        cudaDriverEntryPointQueryResult qr;
        cudaGetDriverEntryPoint("cuTensorMapEncodeTiled", (void**)&enc, cudaEnableDefault, &qr);
        cudaFuncSetAttribute(fused_decode_kernel, cudaFuncAttributeMaxDynamicSharedMemorySize, SMEM_BYTES);
        cudaGetSymbolAddress((void**)&scratch, g_scratch);
    }
    const __nv_bfloat16* x = (const __nv_bfloat16*)d_in[0];
    const __nv_bfloat16* kc = (const __nv_bfloat16*)d_in[1];
    const __nv_bfloat16* vc = (const __nv_bfloat16*)d_in[2];
    const __nv_bfloat16* wq = (const __nv_bfloat16*)d_in[3];
    CUtensorMap mg, mu, mo, md;
    encode(enc, &mg, d_in[6], 2, FF, D_MODEL, 1, FF * 2, 0, 16, 256, 1, CU_TENSOR_MAP_SWIZZLE_32B, CU_TENSOR_MAP_L2_PROMOTION_L2_128B);
    encode(enc, &mu, d_in[7], 2, FF, D_MODEL, 1, FF * 2, 0, 16, 256, 1, CU_TENSOR_MAP_SWIZZLE_32B, CU_TENSOR_MAP_L2_PROMOTION_L2_128B);
    encode(enc, &mo, d_in[4], 3, 64, N_HEAD * DH, 8, D_MODEL * 2, 128, 64, 32, 4, CU_TENSOR_MAP_SWIZZLE_128B, CU_TENSOR_MAP_L2_PROMOTION_NONE);
    encode(enc, &md, d_in[8], 3, D_MODEL, 344, 4, D_MODEL * 2, 344 * D_MODEL * 2, 16, 128, 1, CU_TENSOR_MAP_SWIZZLE_32B, CU_TENSOR_MAP_L2_PROMOTION_L2_128B);
    const __nv_bfloat16* gw = (const __nv_bfloat16*)d_in[9];
    Perm perm = {};
    for (int c = 0; c < NCTA / 2; c++) {
        const int base = c < 36 ? 4 : 36, per = c < 36 ? 8 : 7, q = (c - base) / per, r = (c - base) % per;
        const int v = c < 4 ? c : base + 2 * per * (q >> 1) + 2 * r + (q & 1);
        perm.v[c] = (uint8_t)v;
    }
    Slice slice;
    for (int g = 0, with = 0, without = FF / 16; g < 8; g++)
        for (int b = 0; b < NCTA; b++) {
            const int c = b >> 1;
            if ((c < 4 ? 0 : c < 36 ? (c - 2) & 7 : 1 + (c - 35) % 7) == g)
                slice.v[b] = (uint8_t)((c >= 4 && c < 26) || (b & 1) ? with++ : without++);
        }
    fused_decode_kernel<<<NCTA, NTHREADS, SMEM_BYTES>>>(wq, perm, kc, x, scratch, gw, vc, (__nv_bfloat16*)d_out, slice, mg, mu, mo, md);
}
```
